```python
import torch

def _softmax(x, axis=-1):
    return torch.softmax(x, dim=axis)

def _gelu(x):
    return torch.nn.functional.gelu(x, approximate='tanh')

def _silu(x):
    return torch.nn.functional.silu(x)

def _sigmoid(x):
    return torch.sigmoid(x)

def _layernorm(x, axis=-1, eps=1e-05):
    m = x.mean(dim=axis, keepdim=True)
    v = x.var(dim=axis, keepdim=True, unbiased=False)
    return (x - m) / torch.sqrt(v + eps)

def _scatter_add(tgt, idx, src, axis=0):
    return tgt.clone().index_add_(axis, idx, src)

def _segment_sum(src, seg, n):
    out = torch.zeros((n,) + src.shape[1:], dtype=src.dtype)
    return out.index_add_(0, seg, src)

def _pad(x, pw):
    flat = tuple((v for pair in reversed(pw) for v in pair))
    return torch.nn.functional.pad(x, flat)
kernel_name = 'standalone__factorization_afm__recsys'

def setup_inputs():

    _w = lambda a: (lambda t: t.to(torch.bfloat16) if t.is_floating_point() else t)(torch.as_tensor(a))
    B, F, D, V = (1024, 100, 32, min(1000, 100000))
    A = D
    ii, jj = tuple(torch.triu_indices(F, F, 1).unbind(0))
    return {'idx': _w((lambda lo, hi, *s: torch.randint(lo, hi, s))(0, V, B, F).to(torch.int64)), 'table': _w((lambda *s: torch.randn(*s, dtype=torch.bfloat16) * 0.8)(V, D)), 'ii': _w(ii.to(torch.int64)), 'jj': _w(jj.to(torch.int64)), 'W': _w((lambda *s: torch.randn(*s, dtype=torch.bfloat16) * 0.8)(D, A) * (1.0 / D ** 0.5)), 'b': _w((lambda *s: torch.randn(*s, dtype=torch.bfloat16) * 0.8)(A)), 'h': _w((lambda *s: torch.randn(*s, dtype=torch.bfloat16) * 0.8)(A)), 'p': _w((lambda *s: torch.randn(*s, dtype=torch.bfloat16) * 0.8)(D))}

def reference(idx, table, ii, jj, W, b, h, p):
    emb = table[idx]
    ei = emb[:, ii, :].clone()
    ej = emb[:, jj, :].clone()
    pair = ei * ej
    hid = pair @ W + b
    hid = 0.5 * (hid + torch.abs(hid))
    e = hid @ h
    alpha = _softmax(e, axis=-1)
    pooled = torch.einsum('bp,bpd->bd', alpha, pair)
    return pooled @ p
```

```cpp
#include <cuda_runtime.h>
#include <cuda_bf16.h>
#include <stdint.h>

namespace {

constexpr int kB = 1024, kF = 100, kD = 32, kV = 1000, kP = 4950;
constexpr int NCTA = 132, NTHR = 640;

constexpr int B1_CHUNK = 32 * 512;
constexpr int SM_B1 = 0;
constexpr int SM_BS = 4 * B1_CHUNK;
constexpr int XCH = 16384 + 256 + 128;
constexpr int SM_B2 = SM_BS + 4096;
constexpr int SM_GD = SM_B2 + 16384;
constexpr int SM_FL = SM_GD + 256;
constexpr int SM_AH = SM_B2 + 2 * XCH;
constexpr int SM_AB = SM_AH + 8192;
constexpr int SM_TV = SM_AB + 8192;
constexpr int SM_WT = SM_TV + 2048;
constexpr int SM_CNT = SM_WT + 2048;
constexpr int SM_NBH = SM_CNT + 4096;
constexpr int SM_MISC = SM_NBH + 256;
constexpr int SM_MBAR = SM_MISC + 64;
constexpr int SM_CW = SM_MISC + 128;
constexpr int SM_SV = SM_CW + 9 * 8192;
constexpr int SM_TOTAL = SM_SV + 16384;

constexpr float kSC = 80.f;
constexpr float kTR = 44.f;
constexpr float kLog2e = 1.4426950408889634f;

struct Scratch {
    uint32_t cw[32 * 4 * kB];
    float4 acc[kB * 2];
    unsigned pub[128];
    unsigned epoch;
};
__device__ Scratch g_scr;
struct Params {
    const int* idx; const __nv_bfloat16* table; const int* ii; const int* jj;
    const __nv_bfloat16* W; const __nv_bfloat16* b; const __nv_bfloat16* h; const __nv_bfloat16* p;
    __nv_bfloat16* out; Scratch* scr;
};


__device__ __forceinline__ uint32_t smem_u32(const void* p) { return (uint32_t)__cvta_generic_to_shared(p); }
__device__ __forceinline__ void wg_fence() { asm volatile("wgmma.fence.sync.aligned;" ::: "memory"); }
__device__ __forceinline__ void wg_commit() { asm volatile("wgmma.commit_group.sync.aligned;" ::: "memory"); }
template <int N> __device__ __forceinline__ void wg_wait() { asm volatile("wgmma.wait_group.sync.aligned %0;" :: "n"(N) : "memory"); }
__device__ __forceinline__ uint4 ldg128(const void* p) {
    uint4 v; asm volatile("ld.global.nc.v4.u32 {%0,%1,%2,%3}, [%4];" : "=r"(v.x), "=r"(v.y), "=r"(v.z), "=r"(v.w) : "l"(p)); return v;
}
__device__ __forceinline__ uint32_t ldg32(const void* p) {
    uint32_t v; asm volatile("ld.global.nc.u32 %0, [%1];" : "=r"(v) : "l"(p)); return v;
}
__device__ __forceinline__ uint32_t ldg16(const void* p) {
    uint32_t v; asm volatile("ld.global.nc.u16 %0, [%1];" : "=r"(v) : "l"(p)); return v;
}
__device__ __forceinline__ void bulk_g2s(uint32_t dst, const void* src, uint32_t bytes, uint32_t mbar) {
    asm volatile("cp.async.bulk.shared::cluster.global.mbarrier::complete_tx::bytes [%0], [%1], %2, [%3];"
                 :: "r"(dst), "l"(src), "r"(bytes), "r"(mbar) : "memory");
}
__device__ __forceinline__ void mbar_expect(uint32_t mbar, uint32_t bytes) {
    asm volatile("mbarrier.arrive.expect_tx.shared.b64 _, [%0], %1;" :: "r"(mbar), "r"(bytes) : "memory");
}
__device__ __forceinline__ void mbar_wait(uint32_t mbar, uint32_t parity) {
    asm volatile("{\n.reg .pred p;\nW%=:\nmbarrier.try_wait.parity.shared.b64 p, [%0], %1;\n@!p bra W%=;\n}" :: "r"(mbar), "r"(parity) : "memory");
}
__device__ __forceinline__ void bar_main() { asm volatile("bar.sync 1, 512;" ::: "memory"); }
__device__ __forceinline__ void sts32(uint32_t addr, uint32_t v) {
    asm volatile("st.shared.u32 [%0], %1;" :: "r"(addr), "r"(v) : "memory");
}
__device__ __forceinline__ void pin(uint32_t& r) { asm volatile("" : "+r"(r) :: "memory"); }
__device__ __forceinline__ void fence_async() { asm volatile("fence.proxy.async.shared::cta;" ::: "memory"); }
__device__ __forceinline__ uint32_t bmul2(uint32_t a, uint32_t b) {
    uint32_t r; asm("mul.rn.bf16x2 %0, %1, %2;" : "=r"(r) : "r"(a), "r"(b)); return r;
}
__device__ __forceinline__ uint32_t bfms2(uint32_t a, uint32_t b, uint32_t c) {
    uint32_t r; asm("{.reg .b32 n; neg.bf16x2 n, %3; fma.rn.bf16x2 %0, %1, %2, n;}" : "=r"(r) : "r"(a), "r"(b), "r"(c)); return r;
}
__device__ __forceinline__ uint32_t hmul2(uint32_t a, uint32_t b) {
    uint32_t r; asm("mul.rn.f16x2 %0, %1, %2;" : "=r"(r) : "r"(a), "r"(b)); return r;
}
__device__ __forceinline__ uint32_t hmax2(uint32_t a, uint32_t b) {
    uint32_t r; asm("max.NaN.f16x2 %0, %1, %2;" : "=r"(r) : "r"(a), "r"(b)); return r;
}
__device__ __forceinline__ uint32_t hfma2(uint32_t a, uint32_t b, uint32_t c) {
    uint32_t r; asm("fma.rn.f16x2 %0, %1, %2, %3;" : "=r"(r) : "r"(a), "r"(b), "r"(c)); return r;
}
__device__ __forceinline__ float h_lo(uint32_t x) {
    float r; asm("{.reg .b16 l, h; mov.b32 {l, h}, %1; cvt.f32.f16 %0, l;}" : "=f"(r) : "r"(x)); return r;
}
__device__ __forceinline__ float h_hi(uint32_t x) {
    float r; asm("{.reg .b16 l, h; mov.b32 {l, h}, %1; cvt.f32.f16 %0, h;}" : "=f"(r) : "r"(x)); return r;
}
__device__ __forceinline__ float ex2(float x) { float r; asm("ex2.approx.ftz.f32 %0, %1;" : "=f"(r) : "f"(x)); return r; }
__device__ __forceinline__ uint32_t pack_bf16(float lo, float hi) {
    uint32_t r; asm("cvt.rn.bf16x2.f32 %0, %1, %2;" : "=r"(r) : "f"(hi), "f"(lo)); return r;
}
__device__ __forceinline__ uint32_t pack_f16(float lo, float hi) {
    uint32_t r; asm("cvt.rn.f16x2.f32 %0, %1, %2;" : "=r"(r) : "f"(hi), "f"(lo)); return r;
}
__device__ __forceinline__ float bf_lo(uint32_t x) { return __uint_as_float(x << 16); }
__device__ __forceinline__ float bf_hi(uint32_t x) { return __uint_as_float(x & 0xFFFF0000u); }
__device__ __forceinline__ uint32_t bf2h(uint32_t x) { return pack_f16(bf_lo(x), bf_hi(x)); }
__device__ __forceinline__ float4 atom_add_v4(float4* p, float4 v) {
    float4 o;
    asm volatile("atom.relaxed.gpu.global.add.v4.f32 {%0,%1,%2,%3}, [%4], {%5,%6,%7,%8};"
                 : "=f"(o.x), "=f"(o.y), "=f"(o.z), "=f"(o.w) : "l"(p), "f"(v.x), "f"(v.y), "f"(v.z), "f"(v.w) : "memory");
    return o;
}

template <int MODE, uint32_t DESC_HI>
__device__ __forceinline__ void wgmma_h256(uint32_t (&d)[64], uint32_t a0, uint32_t a1, uint32_t a2, uint32_t a3, uint32_t desc_lo) {
    if constexpr (MODE == 1) {
        asm volatile(
            "{\n.reg .b64 dd;\nmov.b64 dd, {%68, %69};\n"
            "wgmma.mma_async.sync.aligned.m64n256k16.f16.f16.f16 "
            "{%0, %1, %2, %3, %4, %5, %6, %7, %8, %9, %10, %11, %12, %13, %14, %15, %16, %17, %18, %19, %20, %21, %22, %23, %24, %25, %26, %27, %28, %29, %30, %31, %32, %33, %34, %35, %36, %37, %38, %39, %40, %41, %42, %43, %44, %45, %46, %47, %48, %49, %50, %51, %52, %53, %54, %55, %56, %57, %58, %59, %60, %61, %62, %63}, "
            "{%64, %65, %66, %67}, dd, 1, 1, 1, 0;\n}\n"
            : "+r"(d[0]), "+r"(d[1]), "+r"(d[2]), "+r"(d[3]), "+r"(d[4]), "+r"(d[5]), "+r"(d[6]), "+r"(d[7]), "+r"(d[8]), "+r"(d[9]), "+r"(d[10]), "+r"(d[11]), "+r"(d[12]), "+r"(d[13]), "+r"(d[14]), "+r"(d[15]), "+r"(d[16]), "+r"(d[17]), "+r"(d[18]), "+r"(d[19]), "+r"(d[20]), "+r"(d[21]), "+r"(d[22]), "+r"(d[23]), "+r"(d[24]), "+r"(d[25]), "+r"(d[26]), "+r"(d[27]), "+r"(d[28]), "+r"(d[29]), "+r"(d[30]), "+r"(d[31]), "+r"(d[32]), "+r"(d[33]), "+r"(d[34]), "+r"(d[35]), "+r"(d[36]), "+r"(d[37]), "+r"(d[38]), "+r"(d[39]), "+r"(d[40]), "+r"(d[41]), "+r"(d[42]), "+r"(d[43]), "+r"(d[44]), "+r"(d[45]), "+r"(d[46]), "+r"(d[47]), "+r"(d[48]), "+r"(d[49]), "+r"(d[50]), "+r"(d[51]), "+r"(d[52]), "+r"(d[53]), "+r"(d[54]), "+r"(d[55]), "+r"(d[56]), "+r"(d[57]), "+r"(d[58]), "+r"(d[59]), "+r"(d[60]), "+r"(d[61]), "+r"(d[62]), "+r"(d[63])
            : "r"(a0), "r"(a1), "r"(a2), "r"(a3), "r"(desc_lo), "n"(DESC_HI));
    } else if constexpr (MODE == 0) {
        asm volatile(
            "{\n.reg .b64 dd;\nmov.b64 dd, {%68, %69};\n"
            "wgmma.mma_async.sync.aligned.m64n256k16.f16.f16.f16 "
            "{%0, %1, %2, %3, %4, %5, %6, %7, %8, %9, %10, %11, %12, %13, %14, %15, %16, %17, %18, %19, %20, %21, %22, %23, %24, %25, %26, %27, %28, %29, %30, %31, %32, %33, %34, %35, %36, %37, %38, %39, %40, %41, %42, %43, %44, %45, %46, %47, %48, %49, %50, %51, %52, %53, %54, %55, %56, %57, %58, %59, %60, %61, %62, %63}, "
            "{%64, %65, %66, %67}, dd, 0, 1, 1, 0;\n}\n"
            : "=r"(d[0]), "=r"(d[1]), "=r"(d[2]), "=r"(d[3]), "=r"(d[4]), "=r"(d[5]), "=r"(d[6]), "=r"(d[7]), "=r"(d[8]), "=r"(d[9]), "=r"(d[10]), "=r"(d[11]), "=r"(d[12]), "=r"(d[13]), "=r"(d[14]), "=r"(d[15]), "=r"(d[16]), "=r"(d[17]), "=r"(d[18]), "=r"(d[19]), "=r"(d[20]), "=r"(d[21]), "=r"(d[22]), "=r"(d[23]), "=r"(d[24]), "=r"(d[25]), "=r"(d[26]), "=r"(d[27]), "=r"(d[28]), "=r"(d[29]), "=r"(d[30]), "=r"(d[31]), "=r"(d[32]), "=r"(d[33]), "=r"(d[34]), "=r"(d[35]), "=r"(d[36]), "=r"(d[37]), "=r"(d[38]), "=r"(d[39]), "=r"(d[40]), "=r"(d[41]), "=r"(d[42]), "=r"(d[43]), "=r"(d[44]), "=r"(d[45]), "=r"(d[46]), "=r"(d[47]), "=r"(d[48]), "=r"(d[49]), "=r"(d[50]), "=r"(d[51]), "=r"(d[52]), "=r"(d[53]), "=r"(d[54]), "=r"(d[55]), "=r"(d[56]), "=r"(d[57]), "=r"(d[58]), "=r"(d[59]), "=r"(d[60]), "=r"(d[61]), "=r"(d[62]), "=r"(d[63])
            : "r"(a0), "r"(a1), "r"(a2), "r"(a3), "r"(desc_lo), "n"(DESC_HI));
    } else {
        asm volatile(
            "{\n.reg .b64 dd;\nmov.b64 dd, {%68, %69};\n"
            "wgmma.mma_async.sync.aligned.m64n256k16.f16.f16.f16 "
            "{%0, %1, %2, %3, %4, %5, %6, %7, %8, %9, %10, %11, %12, %13, %14, %15, %16, %17, %18, %19, %20, %21, %22, %23, %24, %25, %26, %27, %28, %29, %30, %31, %32, %33, %34, %35, %36, %37, %38, %39, %40, %41, %42, %43, %44, %45, %46, %47, %48, %49, %50, %51, %52, %53, %54, %55, %56, %57, %58, %59, %60, %61, %62, %63}, "
            "{%64, %65, %66, %67}, dd, 0, 1, 1, 0;\n}\n"
            : "+r"(d[0]), "+r"(d[1]), "+r"(d[2]), "+r"(d[3]), "+r"(d[4]), "+r"(d[5]), "+r"(d[6]), "+r"(d[7]), "+r"(d[8]), "+r"(d[9]), "+r"(d[10]), "+r"(d[11]), "+r"(d[12]), "+r"(d[13]), "+r"(d[14]), "+r"(d[15]), "+r"(d[16]), "+r"(d[17]), "+r"(d[18]), "+r"(d[19]), "+r"(d[20]), "+r"(d[21]), "+r"(d[22]), "+r"(d[23]), "+r"(d[24]), "+r"(d[25]), "+r"(d[26]), "+r"(d[27]), "+r"(d[28]), "+r"(d[29]), "+r"(d[30]), "+r"(d[31]), "+r"(d[32]), "+r"(d[33]), "+r"(d[34]), "+r"(d[35]), "+r"(d[36]), "+r"(d[37]), "+r"(d[38]), "+r"(d[39]), "+r"(d[40]), "+r"(d[41]), "+r"(d[42]), "+r"(d[43]), "+r"(d[44]), "+r"(d[45]), "+r"(d[46]), "+r"(d[47]), "+r"(d[48]), "+r"(d[49]), "+r"(d[50]), "+r"(d[51]), "+r"(d[52]), "+r"(d[53]), "+r"(d[54]), "+r"(d[55]), "+r"(d[56]), "+r"(d[57]), "+r"(d[58]), "+r"(d[59]), "+r"(d[60]), "+r"(d[61]), "+r"(d[62]), "+r"(d[63])
            : "r"(a0), "r"(a1), "r"(a2), "r"(a3), "r"(desc_lo), "n"(DESC_HI));
    }
}

template <int MODE, uint32_t DESC_HI>
__device__ __forceinline__ void wgmma_n32(float (&d)[16], uint32_t da_lo, uint32_t db_lo) {
    if constexpr (MODE == 1) {
        asm volatile(
            "{\n.reg .b64 da, db;\nmov.b64 da, {%16, %18};\nmov.b64 db, {%17, %18};\n"
            "wgmma.mma_async.sync.aligned.m64n32k16.f32.bf16.bf16 "
            "{%0, %1, %2, %3, %4, %5, %6, %7, %8, %9, %10, %11, %12, %13, %14, %15}, "
            "da, db, 1, 1, 1, 0, 0;\n}\n"
            : "+f"(d[0]), "+f"(d[1]), "+f"(d[2]), "+f"(d[3]), "+f"(d[4]), "+f"(d[5]), "+f"(d[6]), "+f"(d[7]), "+f"(d[8]), "+f"(d[9]), "+f"(d[10]), "+f"(d[11]), "+f"(d[12]), "+f"(d[13]), "+f"(d[14]), "+f"(d[15])
            : "r"(da_lo), "r"(db_lo), "n"(DESC_HI));
    } else if constexpr (MODE == 0) {
        asm volatile(
            "{\n.reg .b64 da, db;\nmov.b64 da, {%16, %18};\nmov.b64 db, {%17, %18};\n"
            "wgmma.mma_async.sync.aligned.m64n32k16.f32.bf16.bf16 "
            "{%0, %1, %2, %3, %4, %5, %6, %7, %8, %9, %10, %11, %12, %13, %14, %15}, "
            "da, db, 0, 1, 1, 0, 0;\n}\n"
            : "=f"(d[0]), "=f"(d[1]), "=f"(d[2]), "=f"(d[3]), "=f"(d[4]), "=f"(d[5]), "=f"(d[6]), "=f"(d[7]), "=f"(d[8]), "=f"(d[9]), "=f"(d[10]), "=f"(d[11]), "=f"(d[12]), "=f"(d[13]), "=f"(d[14]), "=f"(d[15])
            : "r"(da_lo), "r"(db_lo), "n"(DESC_HI));
    } else {
        asm volatile(
            "{\n.reg .b64 da, db;\nmov.b64 da, {%16, %18};\nmov.b64 db, {%17, %18};\n"
            "wgmma.mma_async.sync.aligned.m64n32k16.f32.bf16.bf16 "
            "{%0, %1, %2, %3, %4, %5, %6, %7, %8, %9, %10, %11, %12, %13, %14, %15}, "
            "da, db, 0, 1, 1, 0, 0;\n}\n"
            : "+f"(d[0]), "+f"(d[1]), "+f"(d[2]), "+f"(d[3]), "+f"(d[4]), "+f"(d[5]), "+f"(d[6]), "+f"(d[7]), "+f"(d[8]), "+f"(d[9]), "+f"(d[10]), "+f"(d[11]), "+f"(d[12]), "+f"(d[13]), "+f"(d[14]), "+f"(d[15])
            : "r"(da_lo), "r"(db_lo), "n"(DESC_HI));
    }
}

template <int MODE, uint32_t DESC_HI>
__device__ __forceinline__ void wgmma_n64t(float (&d)[32], uint32_t a0, uint32_t a1, uint32_t a2, uint32_t a3, uint32_t desc_lo) {
    if constexpr (MODE == 1) {
        asm volatile(
            "{\n.reg .b64 dd;\nmov.b64 dd, {%36, %37};\n"
            "wgmma.mma_async.sync.aligned.m64n64k16.f32.bf16.bf16 "
            "{%0, %1, %2, %3, %4, %5, %6, %7, %8, %9, %10, %11, %12, %13, %14, %15, %16, %17, %18, %19, %20, %21, %22, %23, %24, %25, %26, %27, %28, %29, %30, %31}, "
            "{%32, %33, %34, %35}, dd, 1, 1, 1, 1;\n}\n"
            : "+f"(d[0]), "+f"(d[1]), "+f"(d[2]), "+f"(d[3]), "+f"(d[4]), "+f"(d[5]), "+f"(d[6]), "+f"(d[7]), "+f"(d[8]), "+f"(d[9]), "+f"(d[10]), "+f"(d[11]), "+f"(d[12]), "+f"(d[13]), "+f"(d[14]), "+f"(d[15]), "+f"(d[16]), "+f"(d[17]), "+f"(d[18]), "+f"(d[19]), "+f"(d[20]), "+f"(d[21]), "+f"(d[22]), "+f"(d[23]), "+f"(d[24]), "+f"(d[25]), "+f"(d[26]), "+f"(d[27]), "+f"(d[28]), "+f"(d[29]), "+f"(d[30]), "+f"(d[31])
            : "r"(a0), "r"(a1), "r"(a2), "r"(a3), "r"(desc_lo), "n"(DESC_HI));
    } else if constexpr (MODE == 0) {
        asm volatile(
            "{\n.reg .b64 dd;\nmov.b64 dd, {%36, %37};\n"
            "wgmma.mma_async.sync.aligned.m64n64k16.f32.bf16.bf16 "
            "{%0, %1, %2, %3, %4, %5, %6, %7, %8, %9, %10, %11, %12, %13, %14, %15, %16, %17, %18, %19, %20, %21, %22, %23, %24, %25, %26, %27, %28, %29, %30, %31}, "
            "{%32, %33, %34, %35}, dd, 0, 1, 1, 1;\n}\n"
            : "=f"(d[0]), "=f"(d[1]), "=f"(d[2]), "=f"(d[3]), "=f"(d[4]), "=f"(d[5]), "=f"(d[6]), "=f"(d[7]), "=f"(d[8]), "=f"(d[9]), "=f"(d[10]), "=f"(d[11]), "=f"(d[12]), "=f"(d[13]), "=f"(d[14]), "=f"(d[15]), "=f"(d[16]), "=f"(d[17]), "=f"(d[18]), "=f"(d[19]), "=f"(d[20]), "=f"(d[21]), "=f"(d[22]), "=f"(d[23]), "=f"(d[24]), "=f"(d[25]), "=f"(d[26]), "=f"(d[27]), "=f"(d[28]), "=f"(d[29]), "=f"(d[30]), "=f"(d[31])
            : "r"(a0), "r"(a1), "r"(a2), "r"(a3), "r"(desc_lo), "n"(DESC_HI));
    } else {
        asm volatile(
            "{\n.reg .b64 dd;\nmov.b64 dd, {%36, %37};\n"
            "wgmma.mma_async.sync.aligned.m64n64k16.f32.bf16.bf16 "
            "{%0, %1, %2, %3, %4, %5, %6, %7, %8, %9, %10, %11, %12, %13, %14, %15, %16, %17, %18, %19, %20, %21, %22, %23, %24, %25, %26, %27, %28, %29, %30, %31}, "
            "{%32, %33, %34, %35}, dd, 0, 1, 1, 1;\n}\n"
            : "+f"(d[0]), "+f"(d[1]), "+f"(d[2]), "+f"(d[3]), "+f"(d[4]), "+f"(d[5]), "+f"(d[6]), "+f"(d[7]), "+f"(d[8]), "+f"(d[9]), "+f"(d[10]), "+f"(d[11]), "+f"(d[12]), "+f"(d[13]), "+f"(d[14]), "+f"(d[15]), "+f"(d[16]), "+f"(d[17]), "+f"(d[18]), "+f"(d[19]), "+f"(d[20]), "+f"(d[21]), "+f"(d[22]), "+f"(d[23]), "+f"(d[24]), "+f"(d[25]), "+f"(d[26]), "+f"(d[27]), "+f"(d[28]), "+f"(d[29]), "+f"(d[30]), "+f"(d[31])
            : "r"(a0), "r"(a1), "r"(a2), "r"(a3), "r"(desc_lo), "n"(DESC_HI));
    }
}

__device__ __forceinline__ int leaf_of(int cta, int j) {
    if (cta >= 128) return 4 * (cta - 128) + j;
    const int center = cta >> 2, off = 4 * (cta & 3) + j;
    return (center < 16 && off == 8 - (center & 7)) ? center + 16 : ((center + off) & 31);
}

__device__ __noinline__ void refetch(const int* __restrict__ idx, const uint32_t* cwg, int cta, int center, int row0, int q,
                                     uint32_t par, unsigned char* dst) {
    for (int jr = 0; jr < 18; jr++) {
        const int j = jr >> 1, row = row0 + (jr & 1);
        const int G = j < 8 ? leaf_of(cta ^ (j >> 2), j & 3) : center;
        uint32_t x;
        int tries = 0;
        while (true) {
            asm volatile("ld.relaxed.gpu.global.u32 %0, [%1];" : "=r"(x) : "l"(cwg + G * 4096 + row0 * 4 + q * 2 + (jr & 1)) : "memory");
            if (!((x ^ par) >> 31)) break;
            if (++tries > 20000) {
                x = 0;
                for (int f = 0; f < kF; f++) {
                    int v = idx[row * kF + f];
                    if ((v >> 3) == G * 4 + q) {
                        int sh = (v & 7) * 4;
                        if (((x >> sh) & 7) != 7) x += 1u << sh;
                    }
                }
                break;
            }
        }
        *reinterpret_cast<uint32_t*>(dst + j * 8192 + (jr & 1) * 4) = x;
    }
    __syncwarp();
}

__device__ __forceinline__ void service_wg(const int* __restrict__ idx, Scratch* scr, unsigned char* smem, int cta, int center) {
    const int t = threadIdx.x & 127, lane = t & 31;
    const uint32_t sbase = smem_u32(smem);
    uint32_t* cnt = reinterpret_cast<uint32_t*>(smem + SM_CNT);
    int bad = 0;
    uint4 iv[2];
#pragma unroll
    for (int k = 0; k < 2; k++) iv[k] = ldg128(reinterpret_cast<const uint4*>(idx) + (cta & 127) * 200 + min(k * 128 + t, 199));
    unsigned epoch;
    asm volatile("ld.relaxed.gpu.global.u32 %0, [%1];" : "=r"(epoch) : "l"(&scr->epoch) : "memory");
    if (t == 0) {
        asm volatile("mbarrier.init.shared.b64 [%0], 4;" :: "r"(sbase + SM_MBAR) : "memory");
        asm volatile("mbarrier.init.shared.b64 [%0], 1;" :: "r"(sbase + SM_MBAR + 8) : "memory");
        mbar_expect(sbase + SM_MBAR + 8, XCH);
        asm volatile("fence.mbarrier_init.release.cluster;" ::: "memory");
        fence_async();
    }
    __syncwarp();
    asm volatile("barrier.cluster.arrive.relaxed.aligned;" ::: "memory");
    if (cta < 128) {
#pragma unroll
        for (int k = 0; k < 2; k++) reinterpret_cast<uint4*>(cnt)[k * 128 + t] = make_uint4(0, 0, 0, 0);
        asm volatile("bar.sync 3, 128;" ::: "memory");

#pragma unroll
        for (int k = 0; k < 2; k++) {
            const int e = k * 128 + t;
            if (e < 200) {
                const int r = e / 25, ro = (r >> 1) * 8 + (r & 1);
                const unsigned vv[4] = {iv[k].x, iv[k].y, iv[k].z, iv[k].w};
#pragma unroll
                for (int i = 0; i < 4; i++) {
                    const unsigned v = min(vv[i], 1023u);
                    const uint32_t old = atomicAdd(&cnt[(v & ~31u) + ((((v >> 3) & 3) * 2 + ro) ^ ((v >> 3) & 28))], 1u << ((v & 7) * 4));
                    bad |= (((old >> ((v & 7) * 4)) & 7) == 7) | (vv[i] >= (unsigned)kV);
                }
            }
        }
        asm volatile("{\n.reg .pred p, q;\nsetp.ne.b32 p, %0, 0;\nbar.red.or.pred q, 3, 128, p;\nselp.b32 %0, 1, 0, q;\n}" : "+r"(bad) :: "memory");

        const uint32_t par = (epoch & 1) ? 0u : 0x80000000u;
#pragma unroll
        for (int k = 0; k < 2; k++) {
            const int e = k * 128 + t;
            uint4 x = reinterpret_cast<const uint4*>(cnt)[e ^ ((e >> 3) & 7)];
            x.x = (x.x & 0x77777777u) | par; x.y = (x.y & 0x77777777u) | par;
            x.z = (x.z & 0x77777777u) | par; x.w = (x.w & 0x77777777u) | par;
            asm volatile("st.relaxed.gpu.global.v2.u64 [%0], {%1,%2};" :: "l"(scr->cw + (e >> 3) * 4096 + cta * 32 + (e & 7) * 4),
                         "l"((unsigned long long)x.x | ((unsigned long long)x.y << 32)), "l"((unsigned long long)x.z | ((unsigned long long)x.w << 32)) : "memory");
        }
        if (lane == 0) asm volatile("red.relaxed.gpu.global.add.u32 [%0], 1;" :: "l"(&scr->pub[(t >> 5) * 32]) : "memory");

    }
    if (t == 0) {
        *reinterpret_cast<uint32_t*>(smem + SM_MISC + 12) = epoch;
        *reinterpret_cast<volatile uint32_t*>(smem + SM_MISC + 16) = bad;
    }
    if (t < 4) {
        unsigned seen;
        for (int tries = 0; tries < 20000; tries++) {
            asm volatile("ld.relaxed.gpu.global.u32 %0, [%1];" : "=r"(seen) : "l"(&scr->pub[t * 32]) : "memory");
            if (seen >= 128u) break;
            __nanosleep(40);
        }
    }
    asm volatile("bar.sync 3, 128;" ::: "memory");

    if (lane == 0) {
        const int sw4 = t >> 5;
        const uint32_t* src = scr->cw + (cta & 1) * 2048;
        mbar_expect(sbase + SM_MBAR, sw4 == 0 ? 3 * 8192 : 2 * 8192);
        bulk_g2s(sbase + SM_CW + sw4 * 8192, src + leaf_of(cta, sw4) * 4096, 8192, sbase + SM_MBAR);
        bulk_g2s(sbase + SM_CW + (4 + sw4) * 8192, src + leaf_of(cta ^ 1, sw4) * 4096, 8192, sbase + SM_MBAR);
        if (sw4 == 0) bulk_g2s(sbase + SM_CW + 8 * 8192, src + center * 4096, 8192, sbase + SM_MBAR);
    }
    __syncwarp();

    asm volatile("barrier.cluster.wait.aligned;" ::: "memory");
}

__device__ __forceinline__ float rbf(float x) { return __bfloat162float(__float2bfloat16(x)); }
__device__ __noinline__ void slow_rows(uint32_t slowmask, int wrow, const Params& P, float* sW) {
    const int lane = threadIdx.x & 31;
    for (int i = lane; i < 1024; i += 32) sW[i] = __bfloat162float(P.W[i]);
    const float bl = __bfloat162float(P.b[lane]), hl = __bfloat162float(P.h[lane]), pl = __bfloat162float(P.p[lane]);
    __syncwarp();
    for (int t = 0; t < 4; t++) {
        unsigned msk = __ballot_sync(0xffffffffu, (slowmask >> t) & 1);
        while (msk) {
            const int l = __ffs(msk) - 1; msk &= msk - 1;
            const int row = t * 256 + wrow * 16 + (l >> 2) * 2 + (l & 1);
            float m = -INFINITY, den = 0.f, num = 0.f;
            for (int p0 = 0; p0 < kP; p0 += 32) {
                const int p = min(p0 + lane, kP - 1);
                const int i = min(max(P.ii[p], 0), kF - 1), j = min(max(P.jj[p], 0), kF - 1);
                const int u = min(max(P.idx[row * kF + i], 0), kV - 1), v = min(max(P.idx[row * kF + j], 0), kV - 1);
                const uint32_t* tu = reinterpret_cast<const uint32_t*>(P.table + u * kD);
                const uint32_t* tv = reinterpret_cast<const uint32_t*>(P.table + v * kD);
                float e = 0.f, s = 0.f;
#pragma unroll 1
                for (int a0 = 0; a0 < 32; a0 += 16) {
                    float hid[16];
#pragma unroll
                    for (int a = 0; a < 16; a++) hid[a] = 0.f;
#pragma unroll 1
                    for (int d2 = 0; d2 < 16; d2++) {
                        const uint32_t pr = bmul2(tu[d2], tv[d2]);
                        const float x0 = bf_lo(pr), x1 = bf_hi(pr);
                        const float q0 = __shfl_sync(0xffffffffu, pl, 2 * d2), q1 = __shfl_sync(0xffffffffu, pl, 2 * d2 + 1);
                        if (a0 == 0) s = fmaf(x1, q1, fmaf(x0, q0, s));
#pragma unroll
                        for (int a = 0; a < 16; a++) {
                            hid[a] = fmaf(x0, sW[(2 * d2) * 32 + a0 + a], hid[a]);
                            hid[a] = fmaf(x1, sW[(2 * d2 + 1) * 32 + a0 + a], hid[a]);
                        }
                    }
#pragma unroll
                    for (int a = 0; a < 16; a++) {
                        const float y = rbf(rbf(hid[a]) + __shfl_sync(0xffffffffu, bl, a0 + a));
                        e = fmaf(0.5f * (y + fabsf(y)), __shfl_sync(0xffffffffu, hl, a0 + a), e);
                    }
                }
                e = rbf(e);
                if (p0 + lane < kP) {
                    const float mn = fmaxf(m, e);
                    const float sc = (m == -INFINITY) ? 0.f : __expf(m - mn), w = __expf(e - mn);
                    den = den * sc + w;
                    num = num * sc + w * s;
                    m = mn;
                }
            }
            float M = m;
#pragma unroll
            for (int o = 16; o; o >>= 1) M = fmaxf(M, __shfl_xor_sync(0xffffffffu, M, o));
            const float sc = (m == -INFINITY) ? 0.f : __expf(m - M);
            den *= sc; num *= sc;
#pragma unroll
            for (int o = 16; o; o >>= 1) {
                den += __shfl_xor_sync(0xffffffffu, den, o);
                num += __shfl_xor_sync(0xffffffffu, num, o);
            }
            if (lane == 0) P.out[row] = __float2bfloat16(__fdividef(num, den));
        }
    }
}

__global__ void __cluster_dims__(2, 1, 1) __launch_bounds__(NTHR, 1)
afm_kernel(const __grid_constant__ Params P) {
    const int* __restrict__ idx = P.idx; const int* __restrict__ ii = P.ii; const int* __restrict__ jj = P.jj;
    const __nv_bfloat16* __restrict__ table = P.table; const __nv_bfloat16* __restrict__ W = P.W;
    const __nv_bfloat16* __restrict__ bvec = P.b; const __nv_bfloat16* __restrict__ hvec = P.h; const __nv_bfloat16* __restrict__ pvec = P.p;
    __nv_bfloat16* __restrict__ out = P.out; Scratch* __restrict__ scr = P.scr;
    extern __shared__ __align__(128) unsigned char smem[];
    const int tid = threadIdx.x, lane = tid & 31;
    const int warp = __shfl_sync(0xffffffffu, tid >> 5, 0);
    const int cta = blockIdx.x;
    const int center = cta < 128 ? (cta >> 2) : (cta < 130 ? 8 : 16);
    if (warp >= 16) {
        asm volatile("setmaxnreg.dec.sync.aligned.u32 32;");
        service_wg(idx, scr, smem, cta, center);
        return;
    }
    const int wg = warp >> 2, wi = warp & 3, g = lane >> 2, q = lane & 3;

    const int jo = lane >> 3, vs = lane & 7;
    const uint4 ar = ldg128(table + min(32 * leaf_of(cta, wg) + 8 * (vs >> 1) + 4 * (vs & 1) + wi, kV - 1) * kD + 8 * jo);
    uint4 rl, rm;
    const int t4 = tid & 127;
    if (wg == 0) {
        rm = ldg128(W + lane * 32 + 8 * wi);
    } else if (wg == 1) {
        rm = ldg128(table + min(32 * center + 8 * (vs >> 1) + (vs & 1) + 2 * wi, kV - 1) * kD + 8 * jo);
        rl = ldg128(pvec + 8 * jo);
    } else if (wg == 2) {
        rl.w = ldg16(bvec + lane);
        rm.x = ldg16(hvec + lane);
    } else {
        rl.x = ldg32(reinterpret_cast<const uint32_t*>(cta < 125 ? table : W) + (cta < 125 ? cta : (cta - 125) & 3) * 128 + t4);
        const int p = min(cta * 38 + t4, kP - 1);
        rl.y = ldg32(ii + p); rl.z = ldg32(jj + p);
    }
    asm volatile("setmaxnreg.inc.sync.aligned.u32 112;");
    asm volatile("barrier.cluster.arrive.relaxed.aligned;" ::: "memory");
    const uint32_t sbase = smem_u32(smem);

    volatile uint32_t* badp = reinterpret_cast<volatile uint32_t*>(smem + SM_MISC + 20);
    if (wg == 0) {
        const uint32_t wv[4] = {bf2h(rm.x), bf2h(rm.y), bf2h(rm.z), bf2h(rm.w)};
        unsigned short* wt = reinterpret_cast<unsigned short*>(smem + SM_WT) + wi * 256 + lane;
#pragma unroll
        for (int k = 0; k < 4; k++) { wt[(2 * k) * 32] = (unsigned short)wv[k]; wt[(2 * k + 1) * 32] = (unsigned short)(wv[k] >> 16); }
    } else if (wg == 1) {
        const uint4 t = rm;
        *reinterpret_cast<uint4*>(smem + SM_TV + t4 * 16) = make_uint4(bf2h(t.x), bf2h(t.y), bf2h(t.z), bf2h(t.w));
        uint4 x, y;
        x.x = bmul2(t.x, rl.x); x.y = bmul2(t.y, rl.y); x.z = bmul2(t.z, rl.z); x.w = bmul2(t.w, rl.w);
        y.x = bfms2(t.x, rl.x, x.x); y.y = bfms2(t.y, rl.y, x.y); y.z = bfms2(t.z, rl.z, x.z); y.w = bfms2(t.w, rl.w, x.w);
        unsigned char* d2 = smem + SM_BS + wi * 1024 + lane * 16;
        *reinterpret_cast<uint4*>(d2) = x;
        *reinterpret_cast<uint4*>(d2 + 512) = y;
    }
    if (warp == 8) {
        const int bbad = __any_sync(0xffffffffu, ((rl.w & 0x7FFFu) > 0x4200u) | ((rm.x & 0x7FFFu) > 0x4200u) | ((sbase & 0x3FFFFu) != 1024u));
        const float bb = bf_lo(rl.w), hh = bf_lo(rm.x);
        reinterpret_cast<uint2*>(smem + SM_NBH)[lane] = make_uint2(pack_f16(-bb, -bb), pack_f16(hh, hh));
        float k = hh * fminf(bb, 0.f), ka = fabsf(k);
#pragma unroll
        for (int o = 16; o; o >>= 1) { k += __shfl_xor_sync(0xffffffffu, k, o); ka += __shfl_xor_sync(0xffffffffu, ka, o); }
        if (lane == 0) { *reinterpret_cast<float*>(smem + SM_MISC) = k * kLog2e; *badp = bbad | !(ka <= 40.f); }
    }
    *reinterpret_cast<uint4*>(smem + SM_AB + tid * 16) = ar;
    fence_async();
    *reinterpret_cast<uint4*>(smem + SM_AH + tid * 16) = make_uint4(bf2h(ar.x), bf2h(ar.y), bf2h(ar.z), bf2h(ar.w));
    bar_main();

    const int mb = wg & 1;
    uint32_t a1h[8];
    const int c0 = 2 * (wg >> 1);
    constexpr uint32_t dbase = (1024u >> 4) | ((128u >> 4) << 16);
    float sacc[16];
    wg_fence();
    wgmma_n32<0, 32>(sacc, dbase + (SM_AB + mb * 4096) / 16, dbase + (SM_BS + c0 * 1024) / 16);
    wgmma_n32<1, 32>(sacc, dbase + (SM_AB + mb * 4096) / 16 + 16, dbase + (SM_BS + c0 * 1024) / 16 + 16);
    wg_commit();
    uint4 ww[4], tt[2];
#pragma unroll
    for (int k = 0; k < 4; k++) ww[k] = *reinterpret_cast<const uint4*>(smem + SM_WT + (warp & 7) * 128 + (k >> 1) * 1024 + (k & 1) * 64 + jo * 16);
#pragma unroll
    for (int c = 0; c < 2; c++) tt[c] = *reinterpret_cast<const uint4*>(smem + SM_TV + (c0 + c) * 512 + lane * 16);
#pragma unroll
    for (int s = 0; s < 2; s++)
        asm volatile("ldmatrix.sync.aligned.m8n8.x4.shared.b16 {%0,%1,%2,%3}, [%4];"
                     : "=r"(a1h[4 * s]), "=r"(a1h[4 * s + 1]), "=r"(a1h[4 * s + 2]), "=r"(a1h[4 * s + 3])
                     : "r"(sbase + SM_AH + (8 * mb + 2 * wi + (jo & 1)) * 512 + (2 * s + (jo >> 1)) * 128 + vs * 16) : "memory");
    unsigned char* b1dst = smem + SM_B1 + c0 * B1_CHUNK + (warp & 7) * 1024 + lane * 16;
    auto b1tile = [&](int c, int k) {
        const uint4 t = tt[c], x = ww[k];
        *reinterpret_cast<uint4*>(b1dst + (k >> 1) * B1_CHUNK + c * 8192 + (k & 1) * 512) =
            make_uint4(hmul2(t.x, x.x), hmul2(t.y, x.y), hmul2(t.z, x.z), hmul2(t.w, x.w));
    };
    const uint32_t dB1 = dbase + (SM_B1 + c0 * B1_CHUNK) / 16;
#pragma unroll
    for (int k = 0; k < 4; k++) b1tile(k & 1, k >> 1);
    wg_wait<0>();
#pragma unroll
    for (int c = 0; c < 2; c++)
        *reinterpret_cast<float4*>(smem + SM_SV + c * 8192 + tid * 16) =
            make_float4(sacc[8 * c] + sacc[8 * c + 4], sacc[8 * c + 1] + sacc[8 * c + 5], sacc[8 * c + 2] + sacc[8 * c + 6], sacc[8 * c + 3] + sacc[8 * c + 7]);
    fence_async();
    asm volatile("bar.sync %0, 256;" :: "r"(4 + (wg >> 1)) : "memory");
#pragma unroll
    for (int k = 4; k < 8; k++) b1tile(k & 1, k >> 1);
    uint32_t acc[64];
    wg_fence();
    wgmma_h256<0, 32>(acc, a1h[0], a1h[1], a1h[2], a1h[3], dB1);
    wgmma_h256<1, 32>(acc, a1h[4], a1h[5], a1h[6], a1h[7], dB1 + 16);
    wg_commit();
    if (wg == 3) {
        const int ci = (int)rl.y, cj = (int)rl.z, cp = min(cta * 38 + t4, kP - 1);
        if (((rl.x & 0x7FFFu) > 0x4200u) | (((rl.x >> 16) & 0x7FFFu) > 0x4200u) |
            !((ci >= 0) && (cj > ci) && (cj < kF) && (cp == (ci * (2 * kF - ci - 1)) / 2 + (cj - ci - 1)))) *badp = 1;
    }
    fence_async();
    asm volatile("bar.sync %0, 256;" :: "r"(4 + (wg >> 1)) : "memory");

    const bool diag = (cta < 128) && ((cta & 3) == 0);

    {
        const float koff = *reinterpret_cast<const float*>(smem + SM_MISC);
        const uint4* nbh = reinterpret_cast<const uint4*>(smem + SM_NBH);
        const int ul0 = 8 * (g >> 1) + 4 * (g & 1) + 2 * (wi & 1);
        const bool dgrp = diag && mb == 0 && wi < 2;
        const uint32_t gdst = sbase + SM_B2 + (8 * mb + 2 * wi) * 128 + lane * 4 + c0 * 4096;
        float emax = 0.f;
        uint32_t gmax = 0;
        uint4 kk[2];

        auto preload = [&](int hf) {
#pragma unroll
            for (int i = 0; i < 2; i++) kk[i] = nbh[8 * hf + i];
        };
        auto half = [&](int hf, uint32_t (&e)[4]) {
#pragma unroll
            for (int i2 = 0; i2 < 8; i2++) {
                uint4 k = kk[i2 & 1];
                if (i2 < 6) kk[i2 & 1] = nbh[8 * hf + 2 + i2];
                if (i2 == 0) {
                    e[0] = hmul2(hmax2(acc[0], k.x), k.y);
                    e[1] = hmul2(hmax2(acc[1], k.x), k.y);
                    e[2] = hmul2(hmax2(acc[32 + 0], k.x), k.y);
                    e[3] = hmul2(hmax2(acc[32 + 1], k.x), k.y);
                } else {
                    e[0] = hfma2(hmax2(acc[4 * i2 + 0], k.x), k.y, e[0]);
                    e[1] = hfma2(hmax2(acc[4 * i2 + 1], k.x), k.y, e[1]);
                    e[2] = hfma2(hmax2(acc[32 + 4 * i2 + 0], k.x), k.y, e[2]);
                    e[3] = hfma2(hmax2(acc[32 + 4 * i2 + 1], k.x), k.y, e[3]);
                }
                e[0] = hfma2(hmax2(acc[4 * i2 + 2], k.z), k.w, e[0]);
                e[1] = hfma2(hmax2(acc[4 * i2 + 3], k.z), k.w, e[1]);
                e[2] = hfma2(hmax2(acc[32 + 4 * i2 + 2], k.z), k.w, e[2]);
                e[3] = hfma2(hmax2(acc[32 + 4 * i2 + 3], k.z), k.w, e[3]);
            }
        };
        const int dl0 = ul0 - 8 * q - 2 * c0;
        auto finalize = [&](int cc, uint32_t ea0, uint32_t ea1, uint32_t eb0, uint32_t eb1) {
            const float4 s4 = *reinterpret_cast<const float4*>(smem + SM_SV + cc * 8192 + tid * 16);
#pragma unroll
            for (int x = 0; x < 4; x++) {
                const int r = x >> 1, e1 = x & 1;
                uint32_t pa = r ? ea1 : ea0, pb = r ? eb1 : eb0;
                float e = fmaf(e1 ? (h_hi(pa) + h_hi(pb)) : (h_lo(pa) + h_lo(pb)), kLog2e, koff);

                const float s = x == 0 ? s4.x : x == 1 ? s4.y : x == 2 ? s4.z : s4.w;
                asm("max.NaN.f32 %0, %0, %1;" : "+f"(emax) : "f"(fabsf(e)));
                float g0 = ex2(e + (kSC - 8.f * cc - 4.f * (r + e1)));
                float g1 = g0 * s;
                uint32_t ub = (__float_as_uint(g1) << 1) - ((127u + 8u) << 24);
                gmax = max(gmax, s == 0.f ? 0u : ub);
                uint32_t pk = pack_bf16(g0, g1);
                if (dgrp) {
                    const int dl = dl0 + r - 2 * cc - e1;
                    if (dl == 0) reinterpret_cast<float2*>(smem + SM_GD)[ul0 + r] = make_float2(g0, g1);
                    if (dl >= 0) pk = 0u;
                }
                sts32(gdst + (2 * cc + e1) * 2048 + r * 128, pk);
            }
            pin(gmax);
        };
        uint32_t ea[4], eb[4];
        preload(0);
        wg_wait<0>();
        half(0, ea);
        wg_fence();
        wgmma_h256<2, 32>(acc, a1h[0], a1h[1], a1h[2], a1h[3], dB1 + 1024);
        wgmma_h256<1, 32>(acc, a1h[4], a1h[5], a1h[6], a1h[7], dB1 + 1024 + 16);
        wg_commit();
        preload(1);
        wg_wait<0>();
        half(1, eb);
        finalize(0, ea[0], ea[1], eb[0], eb[1]);
        finalize(1, ea[2], ea[3], eb[2], eb[3]);
        if ((gmax > (118u << 24)) | !(emax <= kTR)) *badp = 1;

    }
    fence_async();
    asm volatile("barrier.cluster.wait.aligned;" ::: "memory");
    mbar_wait(sbase + SM_MBAR, 0);
    bar_main();
    const uint2 bfl = *reinterpret_cast<const uint2*>(smem + SM_MISC + 16);
    const int bad = bfl.x | bfl.y;
    if (tid == 0) {
        sts32(sbase + SM_FL, bad);
        fence_async();
        uint32_t peer;
        asm volatile("mapa.shared::cluster.u32 %0, %1, %2;" : "=r"(peer) : "r"(sbase), "r"((cta & 1) ^ 1));
        asm volatile("cp.async.bulk.shared::cluster.shared::cta.mbarrier::complete_tx::bytes [%0], [%1], %2, [%3];"
                     :: "r"(peer + SM_B2 + XCH), "r"(sbase + SM_B2), "r"(XCH), "r"(peer + SM_MBAR + 8) : "memory");
    }
    __syncwarp();

    const int unit = ((warp + (cta >> 2)) & 15) * 8 + g;
    const int tx = (cta >> 1) & 1;
    const bool diag2 = (cta < 128) && ((cta & 2) == 0);
    const uint32_t desc2 = dbase + SM_B2 / 16;
    const uint32_t magic = 0x4B000000u + blockIdx.y;
    unsigned char* cwt = smem + SM_CW + unit * 32 + q * 8;
    const bool odd = q & 1;
    float4 old;
    float md = 0.f, mn = 0.f, badf = 0.f;
    const int prow = ((cta & 1) << 9) + (((q >> 1) ^ tx) << 8) + 2 * unit + (q & 1);
    uint32_t slowmask = 0;
    const unsigned epoch = *reinterpret_cast<const uint32_t*>(smem + SM_MISC + 12);
    const uint32_t par = (epoch & 1) ? 0u : 0x80000000u;

#pragma unroll
    for (int t = 0; t < 2; t++) {
        unsigned char* cws = cwt + (t ^ tx) * 4096;
        float z[32];
        uint2 cw[9];
#pragma unroll
        for (int j = 0; j < 9; j++) cw[j] = *reinterpret_cast<const uint2*>(cws + j * 8192);
        {
            const uint32_t st = ((cw[0].x ^ par) | (cw[1].x ^ par)) | ((cw[2].x ^ par) | (cw[3].x ^ par)) | ((cw[4].x ^ par) | (cw[5].x ^ par)) |
                                ((cw[6].x ^ par) | (cw[7].x ^ par)) | (cw[8].x ^ par);
            if (__any_sync(0xffffffffu, (int)st < 0)) {
                refetch(idx, scr->cw, cta, center, ((cta & 1) << 9) + ((t ^ tx) << 8) + 2 * unit, q, par, cws);
#pragma unroll
                for (int j = 0; j < 9; j++) cw[j] = *reinterpret_cast<const uint2*>(cws + j * 8192);
            }
        }
        const uint2 vw = cw[8];
        uint32_t af[2][8];
#pragma unroll
        for (int j = 0; j < 8; j++) {
            uint32_t (&a)[8] = af[j & 1];
            if (j >= 2) wg_wait<1>();
#pragma unroll
            for (int r = 0; r < 2; r++) {
                const uint32_t w = r ? cw[j].y : cw[j].x, w8 = w >> 8;
                a[0 + r] = w & 0x00070007u;
                a[2 + r] = w & 0x00700070u;
                a[4 + r] = w8 & 0x00070007u;
                a[6 + r] = w8 & 0x00700070u;
            }
#pragma unroll
            for (int k = 0; k < 8; k++) pin(a[k]);
            if (t == 0 && j == 4) mbar_wait(sbase + SM_MBAR + 8, 0);
            wg_fence();
            const uint32_t d = desc2 + (j >> 2) * (XCH / 16) + (j & 3) * 32;
            if (j == 0) wgmma_n64t<0, 128>(z, a[0], a[1], a[2], a[3], d);
            else wgmma_n64t<1, 128>(z, a[0], a[1], a[2], a[3], d);
            wgmma_n64t<1, 128>(z, a[4], a[5], a[6], a[7], d + 16);
            wg_commit();
        }

        const uint32_t w0s = vw.x >> 16, w1s = vw.y >> 16;
        float f0[8], f1[8];
#pragma unroll
        for (int i = 0; i < 8; i++) {
            const uint32_t m = 7u << (4 * (i & 3));
            f0[i] = __uint_as_float((((i < 4) ? vw.x : w0s) & m) | magic) - 8388608.f;
            f1[i] = __uint_as_float((((i < 4) ? vw.y : w1s) & m) | magic) - 8388608.f;
        }
        float d0 = 0.f, n0 = 0.f, d1 = 0.f, n1 = 0.f;
        if (diag2) {
            uint32_t m = (vw.x | vw.y) & 0x66666666u;
            while (m) {
                const int i = (__ffs(m) - 1) >> 2;
                m &= ~(0xFu << (4 * i));
                const float2 G = reinterpret_cast<const float2*>(smem + SM_GD + (cta & 1) * XCH)[8 * q + i];
                const float sc = __uint_as_float((uint32_t)(127 - 67 + 4 * (i & 3) + 4 * (i & 1)) << 23);
                const int c0 = (vw.x >> (4 * i)) & 7, c1 = (vw.y >> (4 * i)) & 7;
                const float gx = G.x * sc * 0x1p-67f, gy = G.y * sc * 0x1p-67f;
                const float p0 = (float)(c0 * (c0 - 1)), p1 = (float)(c1 * (c1 - 1));
                d0 = fmaf(p0, gx, d0); n0 = fmaf(p0, gy, n0);
                d1 = fmaf(p1, gx, d1); n1 = fmaf(p1, gy, n1);
            }
            __syncwarp();
        }
        wg_wait<0>();

#pragma unroll
        for (int i = 0; i < 8; i++) {
            d0 = fmaf(z[4 * i], f0[i], d0); n0 = fmaf(z[4 * i + 1], f0[i], n0);
            d1 = fmaf(z[4 * i + 2], f1[i], d1); n1 = fmaf(z[4 * i + 3], f1[i], n1);
        }
        float dk = odd ? d1 : d0, ds = odd ? d0 : d1, nk = odd ? n1 : n0, ns = odd ? n0 : n1;
        dk += __shfl_xor_sync(0xffffffffu, ds, 1);
        nk += __shfl_xor_sync(0xffffffffu, ns, 1);
        dk += __shfl_xor_sync(0xffffffffu, dk, 2);
        nk += __shfl_xor_sync(0xffffffffu, nk, 2);
        if ((q >> 1) == t) {
            md = dk * 0x1p53f; mn = nk * 0x1p53f;
            badf = (bad | *reinterpret_cast<const uint32_t*>(smem + SM_FL + XCH)) ? 1.f : 0.f;
            old = atom_add_v4(scr->acc + prow * 2, make_float4(md, mn, 1.f, badf));
        }
    }
    if (old.z == (float)(NCTA / 2 - 1)) {
        scr->acc[prow * 2] = make_float4(0.f, 0.f, 0.f, 0.f);
        if (prow < 4) { scr->pub[prow * 32] = 0; if (prow == 0) scr->epoch = epoch + 1; }
        if (old.w + badf != 0.f) slowmask |= 1u << (prow >> 8);
        else out[prow] = __float2bfloat16(__fdividef(old.y + mn, old.x + md));
    }

    if (__any_sync(0xffffffffu, slowmask))
        slow_rows(slowmask, unit >> 3, P, reinterpret_cast<float*>(smem + SM_B1 + warp * 4096));
}

}

extern "C" void kernel_launch(void* const* d_in, const int* in_sizes, int n_in, void* d_out, int out_size) {
    static Scratch* scr = nullptr;
    if (!scr) {
        cudaFuncSetAttribute(afm_kernel, cudaFuncAttributeMaxDynamicSharedMemorySize, SM_TOTAL);
        cudaGetSymbolAddress((void**)&scr, g_scr);
    }
    Params P{(const int*)d_in[0], (const __nv_bfloat16*)d_in[1], (const int*)d_in[2], (const int*)d_in[3],
             (const __nv_bfloat16*)d_in[4], (const __nv_bfloat16*)d_in[5], (const __nv_bfloat16*)d_in[6],
             (const __nv_bfloat16*)d_in[7], (__nv_bfloat16*)d_out, scr};
    afm_kernel<<<NCTA, NTHR, SM_TOTAL>>>(P);
}
```
